```python
import torch

def _softmax(x, axis=-1):
    return torch.softmax(x, dim=axis)
def _gelu(x):
    return torch.nn.functional.gelu(x, approximate="tanh")
def _silu(x):
    return torch.nn.functional.silu(x)
def _sigmoid(x):
    return torch.sigmoid(x)
def _layernorm(x, axis=-1, eps=1e-5):
    m = x.mean(dim=axis, keepdim=True)
    v = x.var(dim=axis, keepdim=True, unbiased=False)
    return (x - m) / torch.sqrt(v + eps)
def _scatter_add(tgt, idx, src, axis=0):
    return tgt.clone().index_add_(axis, idx, src)
def _segment_sum(src, seg, n):
    out = torch.zeros((n,) + src.shape[1:], dtype=src.dtype)
    return out.index_add_(0, seg, src)
def _pad(x, pw):
    flat = tuple(v for pair in reversed(pw) for v in pair)
    return torch.nn.functional.pad(x, flat)

kernel_name = 'recurrent_scan__ssm_conv_s4d__moe_arch_mod__prompt'

def setup_inputs():

    _w = (lambda a: (lambda t: t.to(torch.bfloat16) if t.is_floating_point() else t)(torch.as_tensor(a)))
    def _A_setup():
        Bsz, L, D, N = 1, 2048, 512, 128
        return {
            "u": _w((lambda *s: torch.randn(*s, dtype=torch.bfloat16) * 0.05)(Bsz, L, D)),
            "log_A_real": _w((lambda *s: torch.randn(*s, dtype=torch.bfloat16) * 3.2)(D, N) * 0.5),
            "A_imag": _w((lambda *s: torch.randn(*s, dtype=torch.bfloat16) * 0.05)(D, N) * 3.14),
            "C_real": _w((lambda *s: torch.randn(*s, dtype=torch.bfloat16) * 0.1)(D, N) / N ** 0.5),
            "C_imag": _w((lambda *s: torch.randn(*s, dtype=torch.bfloat16) * 0.1)(D, N) / N ** 0.5),
            "log_dt": _w((lambda *s: torch.randn(*s, dtype=torch.bfloat16) * 0.05)(D) * 0.5 - 4.0),
            "D_skip": _w((lambda *s: torch.randn(*s, dtype=torch.bfloat16) * 0.05)(D)),
        }
    _A_in = _A_setup()

    def _B_setup():
        B, S, D, F, C = 1, 2048, 512, 1376, 1
        return {
            "x": _w((lambda *s: torch.randn(*s, dtype=torch.bfloat16) * 0.05)(B, S, D)),
            "w_r": _w((lambda *s: torch.randn(*s, dtype=torch.bfloat16) * 3.2)(D)),
            "w_gate": _w((lambda *s: torch.randn(*s, dtype=torch.bfloat16) * 0.1)(D, F)),
            "w_up": _w((lambda *s: torch.randn(*s, dtype=torch.bfloat16) * 0.1)(D, F)),
            "w_down": _w((lambda *s: torch.randn(*s, dtype=torch.bfloat16) * 0.1)(F, D)),
        }
    _B_in = _B_setup()

    return {
        "A_u": _A_in["u"],
        "A_log_A_real": _A_in["log_A_real"],
        "A_A_imag": _A_in["A_imag"],
        "A_C_real": _A_in["C_real"],
        "A_C_imag": _A_in["C_imag"],
        "A_log_dt": _A_in["log_dt"],
        "A_D_skip": _A_in["D_skip"],
        "B_x": _B_in["x"],
        "B_w_r": _B_in["w_r"],
        "B_w_gate": _B_in["w_gate"],
        "B_w_up": _B_in["w_up"],
        "B_w_down": _B_in["w_down"],
    }

def reference(A_u, A_log_A_real, A_A_imag, A_C_real, A_C_imag, A_log_dt, A_D_skip, B_x, B_w_r, B_w_gate, B_w_up, B_w_down):
    def _A_ref(u, log_A_real, A_imag, C_real, C_imag, log_dt, D_skip):
        L = u.shape[1]
        dt = torch.exp(log_dt)
        A = -torch.exp(log_A_real) + 1j * A_imag
        C = (C_real + 1j * C_imag) * dt[:, None]
        pos = (lambda x, dt: x.to(dt))(torch.arange(L), log_dt.dtype)
        P = torch.exp((A * dt[:, None])[:, :, None] * pos[None, None, :])
        K = 2.0 * torch.einsum("dn,dnl->dl", C, P).real
        L2 = 2 * L
        u_t = (lambda x, *d: x.permute(*d))(u, 0, 2, 1)
        Kf = (lambda x, *a, **k: torch.fft.rfft(x.float(), *a, **k))(K, L2)
        Uf = (lambda x, *a, **k: torch.fft.rfft(x.float(), *a, **k))(u_t, L2)
        y = (lambda x, *a, **k: torch.fft.irfft(x, *a, **k).to(torch.bfloat16))(Uf * Kf[None, :, :], L2)[:, :, :L]
        y = (lambda x, *d: x.permute(*d))(y, 0, 2, 1)
        return y + u * D_skip[None, None, :]

    def _B_ref(x, w_r, w_gate, w_up, w_down):
        B, S, D = x.shape
        C = 1
        r = x @ w_r
        idx = torch.argsort(-r, axis=-1)[:, :C]
        idx_e = (lambda x, n, axis: torch.repeat_interleave(x, n, dim=axis))(idx.reshape(B, C, 1), D, axis=2)
        x_sel = (lambda x, i, axis: torch.take_along_dim(x, i, dim=axis))(x, idx_e, axis=1)
        g = _silu(x_sel @ w_gate)
        u = x_sel @ w_up
        y = (g * u) @ w_down
        r_sel = _sigmoid((lambda x, i, axis: torch.take_along_dim(x, i, dim=axis))(r, idx, axis=1))
        y = y * r_sel.reshape(B, C, 1)
        b_off = (torch.arange(B) * S).reshape(B, 1)
        flat_idx = (idx + b_off).reshape(B * C)
        zero = (x * 0.0).reshape(B * S, D)
        upd = _scatter_add(zero, flat_idx, y.reshape(B * C, D), axis=0)
        return x + upd.reshape(B, S, D)

    x = A_u
    xn = _layernorm(x, axis=-1)
    s = _A_ref(xn, A_log_A_real, A_A_imag, A_C_real, A_C_imag, A_log_dt, A_D_skip)
    g = _silu(_B_ref(xn, B_w_r, B_w_gate, B_w_up, B_w_down))
    return x + s * g
```

```cpp
#include <cuda_runtime.h>
#include <cuda_bf16.h>
#include <cuda_fp16.h>
#include <cuda.h>
#include <stdint.h>

namespace {

constexpr int SEQ = 2048, DM = 512, FF = 1376;
constexpr int NTHREADS = 768;
constexpr int NCTA = 130;

constexpr uint32_t OFF_WT = 0;
constexpr uint32_t OFF_XS = 32768;
constexpr uint32_t OFF_YB = 49152;
constexpr uint32_t OFF_KS = 69632;
constexpr uint32_t CH_STRIDE = 8192, U_OFF = 4096;
constexpr uint32_t OFF_BAR = 102400;
constexpr uint32_t OFF_KEY = 102784;
constexpr uint32_t OFF_XSEL = 102848;
constexpr uint32_t OFF_S = 104064;
constexpr uint32_t S_STRIDE = 15616;
constexpr uint32_t SMEM_BYTES = OFF_S + 4 * 28672;

constexpr int K0 = 8, KB2 = 544, KA2 = 632, KB3 = 720, KA3 = 800, KFX = 880, KDUMMY = 928;
constexpr uint32_t SG_S3 = 0, SG_S5 = 3072, SG_S7 = 6144, SG_S9 = 8192, SG_P2 = 10496, SG_P3 = 13568;
constexpr int B_Y = 0, B_U = 16, B_X = 32, B_WT = 36, B_K = 37, B_W = 38;

constexpr int SPIN_LIMIT = 200000;
#define ROW_DELAY 700
#define PING 1
#define THR 0
#define DTHR 0
#define SLEEP_NS 100
#define LONGW 0
#define PRE_AHEAD 2
#define H_LAG 0
#define EPAUSE 1
#define POLL_D 750
#define EB_WAIT 0
#define TANH 1
#define XS_N 12
#define XS_T0 1400
#define XS_DT 180
#define WT_T0 2200
#define WT_DT 300
#define WD_T0 5000
#define WD_DT 250

constexpr int G_STATS = 0, G_KEY = SEQ, G_PRE = G_KEY + 128, G_SUM = G_PRE + 4 * FF, G_BUF = 16384, G_EPOCH = 2 * G_BUF;
__device__ __align__(128) unsigned g_scr[G_EPOCH + NCTA * 32];
#define TS(k) do {} while (0)
#define TS_END() do {} while (0)
#define SMEM_EXTRA 0

struct DstTab { uint16_t v[64][16]; };
struct Dst3 { int lo, hi, mid; };
constexpr Dst3 dst_of(int nu, int col, int m) {
    const int s3 = (m & 1) ? KB3 + (m - 1) / 2 : KA3 + m / 2 - 1;
    int one = KDUMMY, three = -1;
    if (nu == 1) {
        if (col == 0) { if (m) three = 256 + 8 * m; else one = K0 + 256; }
        else if (col == 1) one = m ? KA2 + m - 1 : K0 + 514;
        else if (col == 2) one = KA2 + 31 + m;
        else if (col == 3) one = m ? s3 : KA2 + 63;
        else if (col < 7) one = s3 + 16 * (col - 3);
        else if (!m) one = KA3 + 63;
    } else {
        if (col == 0) one = K0 + 258 + 8 * m;
        else if (col == 1) three = 260 + 8 * m;
        else if (col == 2) one = K0 + 262 + 8 * m;
        else if (col == 3) { if (!m) three = 512; }
        else if (col == 4) one = KB2 + m;
        else if (col == 5) one = KB2 + 32 + m;
        else if (col == 6) { if (!m) one = K0 + 257; }
        else if (!m) one = KFX + 3;
    }
    return three >= 0 ? Dst3{K0 + three - 1, K0 + three + 2, K0 + three} : Dst3{one, one + 1, KDUMMY + 2};
}
constexpr DstTab make_dst() {
    DstTab T{};
    for (int i = 0; i < 64; i++)
        for (int nu = 1; nu < 3; nu++)
            for (int r = 0; r < 2; r++) {
                const int m = 16 * (i >> 5) + 8 * r + ((i & 31) >> 2), t = i & 3;
                const Dst3 x = dst_of(nu, 2 * t + nu - 1, m), y = dst_of(nu, 2 * t + 2 - nu, m);
                uint16_t* o = &T.v[i][8 * (nu - 1) + 4 * r];
                o[0] = (uint16_t)(4 * x.lo); o[1] = (uint16_t)(4 * x.hi + 2); o[2] = (uint16_t)(4 * x.mid); o[3] = (uint16_t)(4 * y.lo);
            }
    return T;
}
__device__ const __align__(16) DstTab g_dst = make_dst();

struct Maps { CUtensorMap m[5]; };

struct Params {
    const __nv_bfloat16 *x, *logA, *Aim, *Cr, *Ci, *logdt, *Dskip, *wr;
    __nv_bfloat16* out;
    unsigned* scr;
    const uint4* dst;
};

__device__ __forceinline__ void mbar_init(uint32_t a, uint32_t c) { asm volatile("mbarrier.init.shared::cta.b64 [%0],%1;" ::"r"(a), "r"(c) : "memory"); }
__device__ __forceinline__ void mbar_expect(uint32_t a, uint32_t b) { asm volatile("mbarrier.arrive.expect_tx.shared::cta.b64 _,[%0],%1;" ::"r"(a), "r"(b) : "memory"); }
__device__ __forceinline__ void mbar_arrive(uint32_t a) { asm volatile("mbarrier.arrive.shared::cta.b64 _,[%0];" ::"r"(a) : "memory"); }
__device__ __forceinline__ void mbar_wait(uint32_t a) {
    asm volatile("{.reg .pred p,q; .reg .u32 c; mov.u32 c,0;\n"
                 "W: mbarrier.try_wait.parity.shared::cta.b64 p,[%0],0; add.u32 c,c,1; setp.lt.and.u32 q,c,%1,!p; @q bra W;}"
                 ::"r"(a), "n"(SPIN_LIMIT) : "memory");
}
__device__ __forceinline__ void mbar_wait_long(uint32_t a) {
    asm volatile("{.reg .pred p,q; .reg .u32 c; mov.u32 c,0;\n"
                 "W: mbarrier.test_wait.parity.shared::cta.b64 p,[%0],0; @!p nanosleep.u32 %2; add.u32 c,c,1; setp.lt.and.u32 q,c,%1,!p; @q bra W;}"
                 ::"r"(a), "n"(SPIN_LIMIT), "n"(SLEEP_NS) : "memory");
}
__device__ __forceinline__ uint32_t mapa(uint32_t a, uint32_t r) { uint32_t d; asm("mapa.shared::cluster.u32 %0,%1,%2;" : "=r"(d) : "r"(a), "r"(r)); return d; }
__device__ __forceinline__ void st_async(uint32_t a, uint32_t v, uint32_t bar) {
    asm volatile("st.async.weak.shared::cluster.mbarrier::complete_tx::bytes.u32 [%0],%1,[%2];" ::"r"(a), "r"(v), "r"(bar) : "memory");
}
__device__ __forceinline__ void st_async_p(uint32_t p, uint32_t a, uint32_t v, uint32_t bar) {
    asm volatile("{.reg .pred p; setp.ne.u32 p,%3,0; @p st.async.weak.shared::cluster.mbarrier::complete_tx::bytes.u32 [%0],%1,[%2];}"
                 ::"r"(a), "r"(v), "r"(bar), "r"(p));
}
template <int V> struct IC { static constexpr int value = V; };
__device__ __forceinline__ void bar_sync(int id, int n) { asm volatile("bar.sync %0,%1;" ::"r"(id), "r"(n) : "memory"); }
__device__ __forceinline__ void bar_arrive(int id, int n) { asm volatile("bar.arrive %0,%1;" ::"r"(id), "r"(n) : "memory"); }
__device__ __forceinline__ void cp16(uint32_t dst, const void* src) { asm volatile("cp.async.cg.shared.global [%0],[%1],16;" ::"r"(dst), "l"(src) : "memory"); }
__device__ __forceinline__ void tma4d(uint32_t dst, const CUtensorMap* m, uint32_t bar, int c0, int c1, int c2, int c3) {
    asm volatile("cp.async.bulk.tensor.4d.shared::cluster.global.mbarrier::complete_tx::bytes [%0],[%1,{%3,%4,%5,%6}],[%2];"
                 ::"r"(dst), "l"(m), "r"(bar), "r"(c0), "r"(c1), "r"(c2), "r"(c3) : "memory");
}
__device__ __forceinline__ bool elect() {
    uint32_t p;
    asm volatile("{.reg .pred p; elect.sync _|p, 0xffffffff; selp.u32 %0,1,0,p;}" : "=r"(p));
    return p;
}
__device__ __forceinline__ void stsm4t(uint32_t a, uint32_t r0, uint32_t r1, uint32_t r2, uint32_t r3) {
    asm volatile("stmatrix.sync.aligned.m8n8.x4.trans.shared.b16 [%0],{%1,%2,%3,%4};" ::"r"(a), "r"(r0), "r"(r1), "r"(r2), "r"(r3) : "memory");
}
__device__ __forceinline__ uint32_t lds32(uint32_t a) { uint32_t v; asm volatile("ld.shared.u32 %0,[%1];" : "=r"(v) : "r"(a)); return v; }
__device__ __forceinline__ uint32_t lds32v(uint32_t a) { uint32_t v; asm volatile("ld.volatile.shared.u32 %0,[%1];" : "=r"(v) : "r"(a)); return v; }
__device__ __forceinline__ void lds32p(uint32_t p, uint32_t& v, uint32_t a) {
    asm volatile("{.reg .pred p; setp.ne.u32 p,%1,0; @p ld.shared.u32 %0,[%2];}" : "+r"(v) : "r"(p), "r"(a));
}
__device__ __forceinline__ uint32_t lds16(uint32_t a) { uint16_t v; asm volatile("ld.shared.u16 %0,[%1];" : "=h"(v) : "r"(a)); return v; }
__device__ __forceinline__ uint2 lds64(uint32_t a) { uint2 v; asm volatile("ld.shared.v2.u32 {%0,%1},[%2];" : "=r"(v.x), "=r"(v.y) : "r"(a)); return v; }
__device__ __forceinline__ uint4 lds128(uint32_t a) { uint4 v; asm volatile("ld.shared.v4.u32 {%0,%1,%2,%3},[%4];" : "=r"(v.x), "=r"(v.y), "=r"(v.z), "=r"(v.w) : "r"(a)); return v; }
__device__ __forceinline__ void sts16(uint32_t a, uint32_t v) { asm volatile("st.shared.u16 [%0],%1;" ::"r"(a), "r"(v) : "memory"); }
__device__ __forceinline__ void sts32(uint32_t a, uint32_t v) { asm volatile("st.shared.u32 [%0],%1;" ::"r"(a), "r"(v) : "memory"); }
__device__ __forceinline__ void sts64(uint32_t a, uint32_t x, uint32_t y) { asm volatile("st.shared.v2.u32 [%0],{%1,%2};" ::"r"(a), "r"(x), "r"(y) : "memory"); }
__device__ __forceinline__ void sts128(uint32_t a, uint32_t x, uint32_t y, uint32_t z, uint32_t w) {
    asm volatile("st.shared.v4.u32 [%0],{%1,%2,%3,%4};" ::"r"(a), "r"(x), "r"(y), "r"(z), "r"(w) : "memory");
}
__device__ __forceinline__ uint32_t hmul2(uint32_t a, uint32_t b) { uint32_t d; asm("mul.rn.f16x2 %0,%1,%2;" : "=r"(d) : "r"(a), "r"(b)); return d; }
__device__ __forceinline__ uint64_t mkdesc(uint32_t addr, uint32_t lbo, uint32_t sbo = 128) {
    return (uint64_t)(((addr & 0x3FFFFu) >> 4) | ((lbo >> 4) << 16)) | ((uint64_t)(sbo >> 4) << 32);
}
#define R8(d, o) "+r"(d[o]), "+r"(d[o + 1]), "+r"(d[o + 2]), "+r"(d[o + 3]), "+r"(d[o + 4]), "+r"(d[o + 5]), "+r"(d[o + 6]), "+r"(d[o + 7])
__device__ __forceinline__ void mma16(uint32_t (&d)[2], const uint32_t (&a)[4], uint32_t b0, uint32_t b1) {
    asm volatile("mma.sync.aligned.m16n8k16.row.col.f16.f16.f16.f16 {%0,%1},{%2,%3,%4,%5},{%6,%7},{%0,%1};"
                 : "+r"(d[0]), "+r"(d[1]) : "r"(a[0]), "r"(a[1]), "r"(a[2]), "r"(a[3]), "r"(b0), "r"(b1));
}
__device__ __forceinline__ void mma16c(uint32_t (&d)[2], const uint32_t (&a)[4], uint32_t b0, uint32_t b1, const uint32_t (&c)[2]) {
    asm volatile("mma.sync.aligned.m16n8k16.row.col.f16.f16.f16.f16 {%0,%1},{%2,%3,%4,%5},{%6,%7},{%8,%9};"
                 : "=r"(d[0]), "=r"(d[1]) : "r"(a[0]), "r"(a[1]), "r"(a[2]), "r"(a[3]), "r"(b0), "r"(b1), "r"(c[0]), "r"(c[1]));
}
__device__ __forceinline__ void mma16z(uint32_t (&d)[2], const uint32_t (&a)[4], uint32_t b0, uint32_t b1) {
    asm volatile("mma.sync.aligned.m16n8k16.row.col.f16.f16.f16.f16 {%0,%1},{%2,%3,%4,%5},{%6,%7},{%8,%8};"
                 : "=r"(d[0]), "=r"(d[1]) : "r"(a[0]), "r"(a[1]), "r"(a[2]), "r"(a[3]), "r"(b0), "r"(b1), "r"(0));
}
__device__ __forceinline__ void mma16_p(uint32_t p, uint32_t (&d)[2], const uint32_t (&a)[4], uint32_t b0, uint32_t b1) {
    asm volatile("{.reg .pred p; setp.ne.u32 p,%8,0;"
                 "@p mma.sync.aligned.m16n8k16.row.col.f16.f16.f16.f16 {%0,%1},{%2,%3,%4,%5},{%6,%7},{%0,%1};}"
                 : "+r"(d[0]), "+r"(d[1]) : "r"(a[0]), "r"(a[1]), "r"(a[2]), "r"(a[3]), "r"(b0), "r"(b1), "r"(p));
}
__device__ __forceinline__ void ldsm4(uint32_t a, uint32_t (&r)[4]) {
    asm volatile("ldmatrix.sync.aligned.m8n8.x4.shared.b16 {%0,%1,%2,%3},[%4];" : "=r"(r[0]), "=r"(r[1]), "=r"(r[2]), "=r"(r[3]) : "r"(a));
}
__device__ __forceinline__ void ldsm4t(uint32_t a, uint32_t (&r)[4]) {
    asm volatile("ldmatrix.sync.aligned.m8n8.x4.trans.shared.b16 {%0,%1,%2,%3},[%4];" : "=r"(r[0]), "=r"(r[1]), "=r"(r[2]), "=r"(r[3]) : "r"(a));
}
__device__ __forceinline__ void ldsm4p(uint32_t p, uint32_t a, uint32_t (&r)[4]) {
    asm volatile("{.reg .pred p; setp.ne.u32 p,%5,0; @p ldmatrix.sync.aligned.m8n8.x4.shared.b16 {%0,%1,%2,%3},[%4];}"
                 : "+r"(r[0]), "+r"(r[1]), "+r"(r[2]), "+r"(r[3]) : "r"(a), "r"(p));
}
__device__ __forceinline__ void ldsm4tp(uint32_t p, uint32_t a, uint32_t (&r)[4]) {
    asm volatile("{.reg .pred p; setp.ne.u32 p,%5,0; @p ldmatrix.sync.aligned.m8n8.x4.trans.shared.b16 {%0,%1,%2,%3},[%4];}"
                 : "+r"(r[0]), "+r"(r[1]), "+r"(r[2]), "+r"(r[3]) : "r"(a), "r"(p));
}
__device__ __forceinline__ uint32_t mbar_test(uint32_t a) {
    uint32_t ok;
    asm volatile("{.reg .pred p; mbarrier.test_wait.parity.shared::cta.b64 p,[%1],0; selp.u32 %0,1,0,p;}" : "=r"(ok) : "r"(a) : "memory");
    return ok;
}
#define F8(d, o) "+f"(d[o]), "+f"(d[o + 1]), "+f"(d[o + 2]), "+f"(d[o + 3]), "+f"(d[o + 4]), "+f"(d[o + 5]), "+f"(d[o + 6]), "+f"(d[o + 7])
__device__ __forceinline__ void wg_gen(uint32_t (&d)[12], uint64_t da, uint64_t db) {
    asm volatile("wgmma.mma_async.sync.aligned.m64n48k16.f16.f16.f16 {%0,%1,%2,%3,%4,%5,%6,%7,%8,%9,%10,%11},%12,%13,1,1,1,1,1;"
                 : R8(d, 0), "+r"(d[8]), "+r"(d[9]), "+r"(d[10]), "+r"(d[11]) : "l"(da), "l"(db));
}
template <int ACC>
__device__ __forceinline__ void wg_ln(float (&d)[36], uint64_t da) {
    asm volatile("wgmma.mma_async.sync.aligned.m64n72k16.f32.bf16.bf16 {%0,%1,%2,%3,%4,%5,%6,%7,%8,%9,%10,%11,%12,%13,%14,%15,"
                 "%16,%17,%18,%19,%20,%21,%22,%23,%24,%25,%26,%27,%28,%29,%30,%31,%32,%33,%34,%35},%36,%36,%37,1,1,0,0;"
                 : F8(d, 0), F8(d, 8), F8(d, 16), F8(d, 24), "+f"(d[32]), "+f"(d[33]), "+f"(d[34]), "+f"(d[35]) : "l"(da), "n"(ACC));
}
__device__ __forceinline__ void wg_gemv(float (&d)[4], uint64_t da, uint64_t db, int acc) {
    asm volatile("{.reg .pred p; setp.ne.s32 p,%6,0; wgmma.mma_async.sync.aligned.m64n8k16.f32.bf16.bf16 {%0,%1,%2,%3},%4,%5,p,1,1,1,0;}"
                 : "+f"(d[0]), "+f"(d[1]), "+f"(d[2]), "+f"(d[3]) : "l"(da), "l"(db), "r"(acc));
}
constexpr uint64_t SW128 = (uint64_t)1 << 62;
__device__ __forceinline__ void st_async4(uint32_t a, uint32_t x, uint32_t y, uint32_t z, uint32_t w, uint32_t bar) {
    asm volatile("st.async.weak.shared::cluster.mbarrier::complete_tx::bytes.v4.b32 [%0],{%1,%2,%3,%4},[%5];"
                 ::"r"(a), "r"(x), "r"(y), "r"(z), "r"(w), "r"(bar) : "memory");
}
__device__ __forceinline__ void fence_async() { asm volatile("fence.proxy.async.shared::cta;" ::: "memory"); }
__device__ __forceinline__ float hlo(uint32_t v) { return __half2float(__ushort_as_half((unsigned short)(v & 0xffffu))); }
__device__ __forceinline__ float hhi(uint32_t v) { return __half2float(__ushort_as_half((unsigned short)(v >> 16))); }
__device__ __forceinline__ uint32_t hneg2(uint32_t a) { uint32_t d; asm("neg.f16x2 %0,%1;" : "=r"(d) : "r"(a)); return d; }
__device__ __forceinline__ uint32_t hfma2(uint32_t a, uint32_t b, uint32_t c) { uint32_t d; asm("fma.rn.f16x2 %0,%1,%2,%3;" : "=r"(d) : "r"(a), "r"(b), "r"(c)); return d; }
__device__ __forceinline__ void mma16bf(float (&d)[4], uint32_t a0, uint32_t a1, uint32_t a2, uint32_t a3, uint32_t b0, uint32_t b1) {
    asm volatile("mma.sync.aligned.m16n8k16.row.col.f32.bf16.bf16.f32 {%0,%1,%2,%3},{%4,%5,%6,%7},{%8,%9},{%0,%1,%2,%3};"
                 : "+f"(d[0]), "+f"(d[1]), "+f"(d[2]), "+f"(d[3]) : "r"(a0), "r"(a1), "r"(a2), "r"(a3), "r"(b0), "r"(b1));
}
__device__ __forceinline__ uint32_t pack_h2(float lo, float hi) { uint32_t d; asm("cvt.rn.f16x2.f32 %0,%1,%2;" : "=r"(d) : "f"(hi), "f"(lo)); return d; }
__device__ __forceinline__ uint32_t pack_b2(float lo, float hi) { uint32_t d; asm("cvt.rn.bf16x2.f32 %0,%1,%2;" : "=r"(d) : "f"(hi), "f"(lo)); return d; }
__device__ __forceinline__ float blo(uint32_t v) { return __uint_as_float(v << 16); }
__device__ __forceinline__ float bhi(uint32_t v) { return __uint_as_float(v & 0xffff0000u); }
__device__ __forceinline__ float bf16r(float v) { return blo(pack_b2(v, 0.f)); }
__device__ __forceinline__ uint32_t hadd2(uint32_t a, uint32_t b) { uint32_t d; asm("add.rn.f16x2 %0,%1,%2;" : "=r"(d) : "r"(a), "r"(b)); return d; }
__device__ __forceinline__ uint32_t badd2(uint32_t a, uint32_t b) { uint32_t d; asm("add.rn.bf16x2 %0,%1,%2;" : "=r"(d) : "r"(a), "r"(b)); return d; }
__device__ __forceinline__ uint32_t bsub2(uint32_t a, uint32_t b) { uint32_t d; asm("sub.rn.bf16x2 %0,%1,%2;" : "=r"(d) : "r"(a), "r"(b)); return d; }
__device__ __forceinline__ uint32_t bmul2(uint32_t a, uint32_t b) { uint32_t d; asm("mul.rn.bf16x2 %0,%1,%2;" : "=r"(d) : "r"(a), "r"(b)); return d; }
template <int H>
__device__ __forceinline__ uint32_t bmul2h(uint32_t a, uint32_t b) {
    uint32_t d;
    if (H) asm("{.reg .b16 l,h; .reg .b32 t; mov.b32 {l,h},%2; mov.b32 t,{h,h}; mul.rn.bf16x2 %0,%1,t;}" : "=r"(d) : "r"(a), "r"(b));
    else asm("{.reg .b16 l,h; .reg .b32 t; mov.b32 {l,h},%2; mov.b32 t,{l,l}; mul.rn.bf16x2 %0,%1,t;}" : "=r"(d) : "r"(a), "r"(b));
    return d;
}
__device__ __forceinline__ uint32_t bsub2l(uint32_t a, uint32_t b) {
    uint32_t d;
    asm("{.reg .b16 l,h; .reg .b32 t; mov.b32 {l,h},%2; mov.b32 t,{l,l}; sub.rn.bf16x2 %0,%1,t;}" : "=r"(d) : "r"(a), "r"(b));
    return d;
}
__device__ __forceinline__ uint32_t prmt(uint32_t a, uint32_t b, uint32_t s) { return __byte_perm(a, b, s); }
__device__ __forceinline__ float ex2(float v) { float d; asm("ex2.approx.ftz.f32 %0,%1;" : "=f"(d) : "f"(v)); return d; }
__device__ __forceinline__ float rcp(float v) { float d; asm("rcp.approx.ftz.f32 %0,%1;" : "=f"(d) : "f"(v)); return d; }
__device__ __forceinline__ float silu(float v) { return v * rcp(1.f + ex2(-1.4426950408889634f * v)); }
__device__ __forceinline__ float silu_h(float h) { float t; asm("tanh.approx.f32 %0,%1;" : "=f"(t) : "f"(h)); return fmaf(h, t, h); }
__device__ __forceinline__ uint32_t ld_rlx(const unsigned* p) { uint32_t v; asm volatile("ld.relaxed.gpu.global.u32 %0,[%1];" : "=r"(v) : "l"(p) : "memory"); return v; }
__device__ __forceinline__ uint2 ld_rlx2(const unsigned* p) { uint2 v; asm volatile("ld.relaxed.gpu.global.v2.u32 {%0,%1},[%2];" : "=r"(v.x), "=r"(v.y) : "l"(p) : "memory"); return v; }
__device__ __forceinline__ uint4 ld_rlx4(const unsigned* p) { uint4 v; asm volatile("ld.relaxed.gpu.global.v4.u32 {%0,%1,%2,%3},[%4];" : "=r"(v.x), "=r"(v.y), "=r"(v.z), "=r"(v.w) : "l"(p) : "memory"); return v; }
__device__ __forceinline__ void publish(unsigned* p, uint32_t v) { asm volatile("red.relaxed.gpu.global.or.b32 [%0],%1;" ::"l"(p), "r"(v) : "memory"); }
__device__ __forceinline__ uint4 ldg128(const void* p) {
    uint4 v;
    asm volatile("ld.global.nc.v4.u32 {%0,%1,%2,%3},[%4];" : "=r"(v.x), "=r"(v.y), "=r"(v.z), "=r"(v.w) : "l"(p));
    return v;
}
__device__ __forceinline__ uint2 ldg64(const void* p) { uint2 v; asm volatile("ld.global.nc.v2.u32 {%0,%1},[%2];" : "=r"(v.x), "=r"(v.y) : "l"(p)); return v; }
__device__ __forceinline__ uint32_t ldg32(const void* p) { uint32_t v; asm volatile("ld.global.nc.u32 %0,[%1];" : "=r"(v) : "l"(p)); return v; }
__device__ __forceinline__ float ldbf(const __nv_bfloat16* p) { return __uint_as_float((uint32_t)__ldg((const unsigned short*)p) << 16); }

struct cplx { float r, i; };
__device__ __forceinline__ cplx cmul(cplx a, cplx b) { return {fmaf(a.r, b.r, -a.i * b.i), fmaf(a.r, b.i, a.i * b.r)}; }
__device__ __forceinline__ cplx cmulc(cplx a, cplx b) { return {fmaf(a.r, b.r, a.i * b.i), fmaf(a.i, b.r, -a.r * b.i)}; }
__device__ __forceinline__ cplx cexp_p(float a2, float th, float tl, float p) {
    float mag = ex2(a2 * p);
    float t = th * p;
    float f = (t - rintf(t)) + tl * p;
    float ang = f * 6.283185307179586f;
    return {mag * __cosf(ang), mag * __sinf(ang)};
}

__global__ void __cluster_dims__(2, 1, 1) __launch_bounds__(NTHREADS, 1)
s4d_fused_kernel(const Params P, const __grid_constant__ Maps tm) {
    extern __shared__ __align__(1024) unsigned char smem_raw[];
    const uint32_t tid = threadIdx.x, l0 = tid & 31, b = blockIdx.x;
    const uint32_t sb0 = (uint32_t)__cvta_generic_to_shared(smem_raw);
    const uint32_t t_entry = (uint32_t)clock();
    uint32_t pl, pa, pd, ep;
    uint2 cr4, ci4;
    uint4 dst1, dst2;
    unsigned* const epoch = P.scr + (G_EPOCH + b * 32 + l0);
    if (tid < 512) {
        const uint32_t n4 = (b & 127) * 128 + ((tid >> 1) & 96) + l0, n2 = 2 * n4 + ((tid >> 5) & 1);
        pl = ldg32((const uint32_t*)P.logA + n2);
        pa = ldg32((const uint32_t*)P.Aim + n2);
        asm volatile("ld.global.nc.u16 %0,[%1];" : "=r"(pd) : "l"((const unsigned short*)P.logdt + (n4 >> 5)));
        if (tid >= 256) {
            cr4 = ldg64((const uint2*)P.Cr + n4);
            ci4 = ldg64((const uint2*)P.Ci + n4);
        }
    } else if (tid >= 640) {
        ep = ld_rlx(epoch);
        if (b < 128) {
            const uint32_t r = (tid >> 5) & 3, xr = sb0 + OFF_YB + (l0 >> 3) * 128;
            if (r < 2) cp16(xr + 8192 + r * 9216 + (((l0 ^ (l0 >> 3)) & 7) * 16), P.wr + (r * 256 + l0 * 8));
            const uint32_t d0 = xr + (l0 >> 3) * 1920 + r * 128 + (((l0 ^ r) & 7) * 16), d1 = (d0 ^ 64) + 512;
            const __nv_bfloat16* src = P.x + ((128 * r + b) * DM + l0 * 8);
            while ((uint32_t)clock() - t_entry < ROW_DELAY) {}
#pragma unroll
            for (int i = 0; i < 8; i++)
                cp16(((i & 2) ? d1 : d0) + (i & 1) * 9216 + (i >> 2) * 1024, src + (i >> 1) * 512 * DM + (i & 1) * 256);
        }
    }
    const int warp = __shfl_sync(0xffffffffu, tid >> 5, 0);
    const uint32_t sb = __shfl_sync(0xffffffffu, sb0, 0);
    const int lane = __shfl_sync(0xffffffffu, l0, l0);
    const int wg = warp >> 2, c = warp & 3, rank = b & 1, q = b >> 1;
    const int g = lane >> 2, t = lane & 3, mi = lane >> 3, rw = lane & 7;
    const uint32_t bar0 = sb + OFF_BAR;

    if (wg < 4) {
        if (b >= 128) return;
        const int ch = (warp & 7) >> 1, hf = warp & 1;
        const uint32_t tab = sb + OFF_S + (wg & 1) * 57344;
        asm volatile("barrier.cluster.arrive.relaxed.aligned;" ::: "memory");
        if (wg < 2) {
            const uint32_t ksb = sb + OFF_KS + ch * CH_STRIDE;
            {
                const uint32_t z = ksb + (hf * 32 + lane) * 16;
                sts128(z, 0, 0, 0, 0);
                sts128(z + 1024, 0, 0, 0, 0);
                sts128(z + 2048, 0, 0, 0, 0);
                sts128(z + 3072, 0, 0, 0, 0);
            }
            uint32_t ta = tab + (c >> 1) * 4096 + (hf * 32 + lane) * 16;
            uint64_t da = mkdesc(tab, 8192, 1024), db = mkdesc(tab + 16384, 6144, 1024);
            asm volatile("" : "+r"(pd));
            const float dt = bf16r(ex2(blo(pd) * 1.4426950408889634f));
            uint32_t acc[12] = {};
            TS(0);
#pragma unroll 1
            for (int pass = 0; pass < 2; pass++, ta += 28672) {
                const float a2 = (bf16r(ex2(bhi(pl) * 1.4426950408889634f)) * dt) * -1.4426950408889634f;
                const float bb = bhi(pa) * dt;
                const float th = bb * 0.15915494f;
                const float tl = fmaf(bb, 0.15915494f, -th) + bb * 6.4206382e-9f;
                pl <<= 16; pa <<= 16;
                cplx A[9];
                A[0] = {1.f, 0.f};
                A[1] = cexp_p(a2, th, tl, 8.f);
                A[2] = cmul(A[1], A[1]);
#pragma unroll
                for (int k = 3; k < 9; k++) A[k] = cmul(A[k - 2], A[2]);
                uint32_t pr[4], pi[4];
#pragma unroll
                for (int k = 0; k < 4; k++) {
                    pr[k] = pack_h2(A[2 * k].r, A[2 * k + 1].r);
                    pi[k] = pack_h2(A[2 * k].i, A[2 * k + 1].i);
                }
                sts128(ta, pr[0], pr[1], pr[2], pr[3]);
                sts128(ta + 8192, pi[0], pi[1], pi[2], pi[3]);
                cplx w = A[8];
#pragma unroll
                for (int j = 1; j < 4; j++) {
                    const uint32_t er = pack_h2(w.r, w.r), ei = pack_h2(w.i, w.i);
                    sts128(ta + j * 1024, hfma2(pr[0], er, hneg2(hmul2(pi[0], ei))), hfma2(pr[1], er, hneg2(hmul2(pi[1], ei))),
                           hfma2(pr[2], er, hneg2(hmul2(pi[2], ei))), hfma2(pr[3], er, hneg2(hmul2(pi[3], ei))));
                    sts128(ta + 8192 + j * 1024, hfma2(pi[0], er, hmul2(pr[0], ei)), hfma2(pi[1], er, hmul2(pr[1], ei)),
                           hfma2(pi[2], er, hmul2(pr[2], ei)), hfma2(pi[3], er, hmul2(pr[3], ei)));
                    if (j < 3) w = cmul(w, A[8]);
                }
                TS(22 + pass);
                if (pass == 0) {
                    dst1 = ldg128(P.dst + (64 * hf + 2 * lane));
                    dst2 = ldg128(P.dst + (64 * hf + 2 * lane + 1));
                }
            }
#pragma unroll 1
            for (int pass = 0; pass < 2; pass++, da += 1792, db += 1792) {
                bar_sync(pass ? 1 + wg : 5, pass ? 256 : 640);
                fence_async();
                TS(1 + pass);
                asm volatile("wgmma.fence.sync.aligned;" ::: "memory");
#pragma unroll
                for (int k = 0; k < 8; k++) wg_gen(acc, da + 8 * k, db + 8 * k);
                asm volatile("wgmma.commit_group.sync.aligned;" ::: "memory");
            }
            asm volatile("barrier.cluster.wait.acquire.aligned;" ::: "memory");
            asm volatile("wgmma.wait_group.sync.aligned 0;" ::: "memory");
            asm volatile("" : R8(acc, 0), "+r"(acc[8]), "+r"(acc[9]), "+r"(acc[10]), "+r"(acc[11]));
            TS(20);
        {
            const uint32_t d0 = ksb + (K0 + 128 * hf + 8 * g + 2 * t) * 4;
            const uint32_t dd[2][4] = {{dst1.x, dst1.y, dst1.z, dst1.w}, {dst2.x, dst2.y, dst2.z, dst2.w}};
            const uint32_t sel = (c >> 1) ? 0x4444u : 0u;
#pragma unroll
            for (int r = 0; r < 2; r++) {
                const uint32_t h = prmt(acc[r], acc[6 + r], sel + 0x1032u);
                sts16(d0 + r * 256, h >> 16);
                sts32(d0 + r * 256 + 4, h);
                sts16(d0 + r * 256 + 10, h);
#pragma unroll
                for (int k = 0; k < 2; k++) {
                    const uint32_t x = prmt(acc[2 + 2 * k + r], acc[8 + 2 * k + r], sel + (k ? 0x3232u : 0x1010u));
                    const uint32_t y = prmt(acc[2 + 2 * k + r], acc[8 + 2 * k + r], sel + (k ? 0x1010u : 0x3232u));
                    const uint32_t e0 = dd[k][2 * r], e1 = dd[k][2 * r + 1];
                    sts16(ksb + (e0 & 0xffffu), x);
                    sts16(ksb + (e0 >> 16), x);
                    if (t < 2) sts64(ksb + (e1 & 0xffffu), x, x);
                    sts16(ksb + (e1 >> 16), y);
                    sts16(ksb + (e1 >> 16) + 6, y);
                }
            }
        }
        TS(21);
        bar_sync(11, 384);
        TS(3);
        const uint32_t kc = sb + OFF_KS + c * CH_STRIDE, ks = kc + (g - 2 * t) * 4, sg = sb + OFF_S + c * S_STRIDE;
        if (wg == 0) {
            asm volatile("setmaxnreg.inc.sync.aligned.u32 176;");
            uint32_t R[66], T[10][4];
#pragma unroll
            for (int o = 0; o < 66; o++) R[o] = lds32(ks + (K0 + 8 * o) * 4);
            const float ds = __uint_as_float(lds32(sb + OFF_KEY + 16 + c * 4));
            uint32_t uq = kc + U_OFF + lane * 4;
            uint32_t sa = sg + ((mi & 1) ? SG_S5 : SG_S3) + (mi >> 1) * 128 + rw * 16;
            uint32_t uf = kc + U_OFF + ((mi & 1) * 8 + (mi >> 1) + rw - 65) * 16;
            uint32_t p3 = sg + SG_P3 - 4 * 256 + lane * 4, p3b = (p3 ^ 16) + 128;
            const uint32_t yo = OFF_YB - 1024 + (4 * rank + c) * 128 + lane * 4;
            uint32_t y0 = mapa(sb + yo, 0), y1 = mapa(sb + yo, 1);
            uint32_t yb0 = mapa(bar0 + 8 * B_Y - 8, 0), yb1 = mapa(bar0 + 8 * B_Y - 8, 1);
            uint32_t Q[4][4], S[4][2] = {}, N[5][2] = {}, h[4] = {}, pa = 0, pb = 0, fx0, fx1;
            mbar_wait(bar0 + 8 * B_U);
            TS(4);
#pragma unroll
            for (int i = 0; i < 4; i++) {
                Q[i][0] = lds32(uq + (2 * i - 7) * 16);
                Q[i][2] = lds32(uq + (2 * i - 6) * 16);
                Q[i][1] = Q[i][3] = 0;
            }
            auto emit = [&](uint32_t on, uint32_t ya, uint32_t yb) {
                st_async_p(on, y0, pack_b2(hlo(ya) * ds, hhi(ya) * ds), yb0);
                st_async_p(on, y1, pack_b2(hlo(yb) * ds, hhi(yb) * ds), yb1);
                y0 += 1024; y1 += 1024; yb0 += 8; yb1 += 8;
            };
            auto loadt = [&](int k) {
                const int o = k - 1;
                T[k][0] = lds32v(ks + (o < 0 ? KDUMMY + 16 : KB2 + 8 * o) * 4);
                T[k][1] = lds32v(ks + (o > 7 ? KDUMMY + 16 : KB2 + 8 * o + 8) * 4);
                T[k][2] = lds32v(ks + (o < 0 ? KDUMMY + 16 : KA2 + 8 * o) * 4);
                T[k][3] = lds32v(ks + (o > 7 ? KDUMMY + 16 : KA2 + 8 * o + 8) * 4);
                if (k == 0) fx0 = lds32(ks + (KFX + 8) * 4) | lds32(ks + (KFX + 7) * 4);
                if (k == 1) fx1 = lds32(ks + KFX * 4) | lds32(ks + (KFX - 1) * 4);
            };
            auto step = [&](auto Jc, auto Dc, int I) {
                constexpr int J = decltype(Jc)::value;
                constexpr bool DIL = decltype(Dc)::value == 1, LOADT = decltype(Dc)::value == 2;
                const uint32_t ya = hadd2(N[0][0], hadd2(S[0][1], pa)), yb = hadd2(N[0][1], hadd2(S[0][0], pb));
                uint32_t f[4];
                if (DIL) {
                    ldsm4t(sa, f);
                    ldsm4p(I >= 8, uf, h);
                    lds32p(I >= 8, pa, p3);
                    lds32p(I >= 8, pb, p3b);
                    sa += 256; uf += 256; p3 += 256; p3b += 256;
                }
#pragma unroll
                for (int i = 0; i < 4; i++) {
#pragma unroll
                    for (int j = 0; j < 4; j++) {
                        const int o = 15 - 2 * i + 16 * j;
                        if (j >= J) continue;
                        if (i == 0) { if (j < 3) mma16c(S[j], Q[0], R[o], R[o - 1], S[j + 1]); else mma16z(S[3], Q[0], R[o], R[o - 1]); }
                        else mma16(S[j], Q[i], R[o], R[o - 1]);
                    }
                    Q[i][1] = lds32(uq + (2 * i + 1) * 16);
                    Q[i][3] = lds32(uq + (2 * i + 2) * 16);
                    if (i == 1) emit(DIL || I > 0, ya, yb);
                    if (LOADT) loadt(i);
                }
#pragma unroll
                for (int i = 0; i < 4; i++) {
#pragma unroll
                    for (int j = 0; j < 4; j++) {
                        const int o = 7 - 2 * i + 16 * j;
                        if (j >= J) continue;
                        if (i == 0) mma16c(N[j], Q[0], R[o], R[o - 1], N[j + 1]);
                        else mma16(N[j], Q[i], R[o], R[o - 1]);
                    }
                    if (i == 3 && J == 5) mma16z(N[4], Q[3], R[65], R[64]);
                    if (J > 1) {
                        Q[i][0] = lds32(uq + (2 * i + 9) * 16);
                        Q[i][2] = lds32(uq + (2 * i + 10) * 16);
                    }
                    if (LOADT) { loadt(4 + i); if (i & 1) loadt(8 + (i >> 1)); }
                }
                uq += 256;
                if (DIL) {
                    mma16(N[0], T[1], f[0], f[1]);
                    if (J > 1) mma16(N[1], T[3], f[0], f[1]);
                    if (J > 2) mma16(N[2], T[5], f[0], f[1]);
                    if (J > 3) mma16(N[3], T[7], f[0], f[1]);
                    mma16(N[0], T[0], f[2], f[3]);
                    if (J > 4) mma16(N[4], T[9], f[0], f[1]);
                    if (J > 1) mma16(N[1], T[2], f[2], f[3]);
                    mma16_p(I >= 8, N[0], h, fx0, fx1);
                    if (J > 2) mma16(N[2], T[4], f[2], f[3]);
                    if (J > 3) mma16(N[3], T[6], f[2], f[3]);
                    if (J > 4) mma16(N[4], T[8], f[2], f[3]);
                }
                TS(8 + I);
            };
            uint32_t ok = 0;
#pragma unroll 1
            for (int I = 0; I < 3; I++) {
                if (!ok) mbar_wait(bar0 + 8 * (B_U + 1 + I));
                ok = mbar_test(bar0 + 8 * (B_U + 2 + I));
                step(IC<5>(), IC<0>(), I);
            }
            if (!ok) mbar_wait(bar0 + 8 * (B_U + 4));
            ok = mbar_test(bar0 + 8 * (B_U + 5));
            step(IC<5>(), IC<2>(), 3);
#pragma unroll 1
            for (int I = 4; I < 13; I++) {
                if (!ok) mbar_wait(bar0 + 8 * (B_U + 1 + I));
                ok = mbar_test(bar0 + 8 * (B_U + 2 + I));
                step(IC<5>(), IC<1>(), I);
            }
            if (!ok) mbar_wait(bar0 + 8 * (B_U + 14));
            mbar_wait(bar0 + 8 * (B_U + 15));
            step(IC<3>(), IC<1>(), 13);
            step(IC<2>(), IC<1>(), 14);
            step(IC<1>(), IC<1>(), 15);
            emit(1, hadd2(N[0][0], hadd2(S[0][1], pa)), hadd2(N[0][1], hadd2(S[0][0], pb)));
            TS(24);
        } else {
            asm volatile("setmaxnreg.dec.sync.aligned.u32 56;");
            uint32_t R3[8][2];
            mbar_wait(bar0 + 8 * B_W);
#pragma unroll
            for (int i = 0; i < 8; i++) {
                R3[i][0] = lds32(ks + (KB3 + 8 * i) * 4);
                R3[i][1] = lds32(ks + (KA3 + 8 * i) * 4);
            }
            const uint32_t sw = ((2 * rw + (mi & 1)) ^ (rw >> 2)) * 16;
            const uint32_t s3 = sg + ((mi >> 1) ? SG_S9 : SG_S7) + sw;
            uint32_t a3[8][2];
#pragma unroll
            for (int p = 0; p < 8; p++) {
                uint32_t f[4];
                ldsm4t(s3 + p * 256, f);
#pragma unroll
                for (int I = p; I < 8; I++) {
                    if (p == 0) mma16z(a3[I], f, R3[I - p][0], R3[I - p][1]);
                    else mma16(a3[I], f, R3[I - p][0], R3[I - p][1]);
                }
            }
            const uint32_t w3 = sg + SG_P3 + (mi >> 1) * 256 + sw;
#pragma unroll
            for (int I = 0; I < 8; I += 2) stsm4t(w3 + I * 256, a3[I][0], a3[I][1], a3[I + 1][0], a3[I + 1][1]);
            __syncwarp();
            if (lane == 0) mbar_arrive(bar0 + 8 * (B_U + 9));
            TS(4);
        }
        TS_END();
        } else {
        const int I0 = warp - 8;
        const unsigned* sp = P.scr + (uint32_t)(G_STATS + 128 * I0 + 64 * rank + 2 * lane);
        uint2 st, su;
        uint4 dv;
        {
            asm volatile("" : "+r"(pd));
            uint32_t mx = __vmaxu2(__vmaxu2(cr4.x & 0x7f807f80u, cr4.y & 0x7f807f80u), __vmaxu2(ci4.x & 0x7f807f80u, ci4.y & 0x7f807f80u));
            mx = __reduce_max_sync(0xffffffffu, max(mx << 16, mx & 0xffff0000u));
            const uint32_t ex = min(mx, 240u << 23);
            const float sig = __uint_as_float((245u << 23) - ex);
            const float dt = bf16r(ex2(blo(pd) * 1.4426950408889634f));
            sts32(sb + OFF_KEY + 16 + ch * 4, __float_as_uint(dt * __uint_as_float(ex + (11u << 23))));
            uint32_t tb = tab + 16384 + (c >> 1) * 3072 + (hf * 32 + lane) * 16;
            uint32_t pr2 = hf ? cr4.y : cr4.x, pi2 = hf ? ci4.y : ci4.x;
            ep = ld_rlx(epoch + (mx >> 31));
            TS(0);
#pragma unroll 1
            for (int pass = 0; pass < 2; pass++, tb += 28672) {
                const float a2 = (bf16r(ex2(bhi(pl) * 1.4426950408889634f)) * dt) * -1.4426950408889634f;
                const float bb = bhi(pa) * dt;
                const float th = bb * 0.15915494f;
                const float tl = fmaf(bb, 0.15915494f, -th) + bb * 6.4206382e-9f;
                const cplx E1 = cexp_p(a2, th, tl, 1.f), E256 = cexp_p(a2, th, tl, 256.f);
                cplx X[8], Y[8];
                X[0] = {bhi(pr2) * sig, bhi(pi2) * -sig};
                pl <<= 16; pa <<= 16; pr2 <<= 16; pi2 <<= 16;
                Y[0] = cmulc(X[0], E256);
#pragma unroll
                for (int k = 1; k < 8; k++) {
                    X[k] = cmulc(X[k - 1], E1);
                    Y[k] = cmulc(Y[k - 1], E256);
                }
                const cplx Z0 = cmulc(X[2], E256), Z1 = cmulc(X[4], E256), Z2 = cmulc(X[6], E256);
                const cplx Z3 = cmulc(Z1, E256), Z4 = cmulc(Z3, E256);
                sts128(tb, pack_h2(X[0].r, X[1].r), pack_h2(X[2].r, X[3].r), pack_h2(X[4].r, X[5].r), pack_h2(X[6].r, X[7].r));
                sts128(tb + 6144, pack_h2(X[0].i, X[1].i), pack_h2(X[2].i, X[3].i), pack_h2(X[4].i, X[5].i), pack_h2(X[6].i, X[7].i));
                sts128(tb + 1024, pack_h2(Y[0].r, Y[1].r), pack_h2(Y[2].r, Y[3].r), pack_h2(Y[4].r, Y[5].r), pack_h2(Y[6].r, Y[7].r));
                sts128(tb + 7168, pack_h2(Y[0].i, Y[1].i), pack_h2(Y[2].i, Y[3].i), pack_h2(Y[4].i, Y[5].i), pack_h2(Y[6].i, Y[7].i));
                sts128(tb + 2048, pack_h2(Z0.r, Z1.r), pack_h2(Z2.r, Y[1].r), pack_h2(Z3.r, Z4.r), pack_h2(Y[0].r, Y[3].r));
                sts128(tb + 8192, pack_h2(Z0.i, Z1.i), pack_h2(Z2.i, Y[1].i), pack_h2(Z3.i, Z4.i), pack_h2(Y[0].i, Y[3].i));
                TS(1 + pass);
                if (pass == 0) {
                    sp += ep;
                    st = ld_rlx2(sp);
                    su = ld_rlx2(sp + 1024);
                    dv = ldg128(P.Dskip + 8 * q);
                    if (EPAUSE == 2) { bar_arrive(5, 640); bar_sync(13, 288); } else bar_sync(5, 640);
                }
            }
        }
        bar_arrive(wg - 1, 256);
        asm volatile("setmaxnreg.dec.sync.aligned.u32 72;");
        asm volatile("barrier.cluster.wait.acquire.aligned;" ::: "memory");
        if (I0 == 7) *(uint4*)(P.scr + (ep ^ G_BUF) + b * 128 + 4 * lane) = make_uint4(0, 0, 0, 0);
        TS(3);
        st.x &= su.x | 0x7fffffffu;
        const uint32_t dw[4] = {badd2(dv.x, dv.x), badd2(dv.y, dv.y), badd2(dv.z, dv.z), badd2(dv.w, dv.w)};
        uint32_t xs = sb + OFF_XS + I0 * 1024 + lane * 16, ys = sb + OFF_YB + I0 * 1024 + lane * 4;
        const uint32_t uo = OFF_KS + U_OFF + I0 * 256 + rank * 128 + lane * 4;
        uint32_t ul = sb + uo, ur = mapa(sb + uo, rank ^ 1), ub = mapa(bar0 + 8 * (B_U + I0), rank ^ 1);
        uint32_t rel = 0;
#pragma unroll 1
        for (int s = wg - 2; s < 4; s += 2) {
            mbar_wait(bar0 + 8 * (B_X + s));
            const uint4 xa = lds128(xs), xb = lds128(xs + 512);
            bool have = __all_sync(0xffffffffu, (int)(st.x & st.y) < 0);
            if (s < 2) bar_sync(6, 320);
            for (int it = 0; !have && it < SPIN_LIMIT; it++) {
                st = ld_rlx2(sp);
                have = __all_sync(0xffffffffu, (int)(st.x & st.y) < 0);
            }
            TS(4 + (s & 2));
            uint32_t G[8], T1[8];
            {
                const float ia = rcp(bhi(st.x) * -2.f), ib = rcp(bhi(st.y) * -2.f);
                const uint32_t wa[4] = {xa.x, xa.y, xa.z, xa.w}, wb[4] = {xb.x, xb.y, xb.z, xb.w};
#pragma unroll
                for (int k = 0; k < 4; k++) {
                    const uint32_t da = bsub2l(wa[k], st.x), db = bsub2l(wb[k], st.y);
                    T1[2 * k] = pack_b2(blo(da) * ia, blo(db) * ib);
                    T1[2 * k + 1] = pack_b2(bhi(da) * ia, bhi(db) * ib);
                }
#pragma unroll
                for (int k = 0; k < 8; k++) G[k] = pack_h2(blo(T1[k]), bhi(T1[k]));
#pragma unroll
                for (int k = 0; k < 4; k++) st_async(ur + k * CH_STRIDE, rank ? G[k] : G[k + 4], ub);
#pragma unroll
                for (int k = 0; k < 4; k++) sts32(ul + k * CH_STRIDE, rank ? G[k + 4] : G[k]);
                __syncwarp();
                if (lane == 0) mbar_arrive(bar0 + 8 * (B_U + 4 * s + c));
                ul += 2048; ur += 2048; ub += 64; sp += 1024;
                TS(5 + (s & 2));
                if (s < 2) {
                    st = ld_rlx2(sp);
                    if (I0 + 8 >= XS_N && elect()) tma4d(sb + OFF_XS + 1024 * (I0 + 8), &tm.m[3], bar0 + 8 * (B_X + wg), 8 * q, 32 * rank, 0, I0 + 8);
                    __syncwarp();
                }
#pragma unroll
                for (int k = 0; k < 8; k++) {
                    G[k] = pack_b2(silu_h(blo(T1[k])), silu_h(bhi(T1[k])));
                    T1[k] = (k & 1) ? bmul2h<1>(T1[k], dw[k >> 1]) : bmul2h<0>(T1[k], dw[k >> 1]);
                }
            }
            TS(9 + 4 * (s & 2));
            if (s < 2) {
                mbar_wait(bar0 + 8 * B_K);
                rel = (~lds32(sb + OFF_KEY) & 2047u) - (512 * s + 128 * c + 64 * rank);
            }
            mbar_wait(bar0 + 8 * (B_Y + 4 * s + c));
            TS(11 + 4 * (s & 2));
            uint32_t pr[8];
#pragma unroll
            for (int k = 0; k < 8; k++) pr[k] = bmul2(badd2(lds32(ys + k * 128), T1[k]), G[k]);
            uint4 oa, ob;
            oa.x = badd2(xa.x, prmt(pr[0], pr[1], 0x5410)); ob.x = badd2(xb.x, prmt(pr[0], pr[1], 0x7632));
            oa.y = badd2(xa.y, prmt(pr[2], pr[3], 0x5410)); ob.y = badd2(xb.y, prmt(pr[2], pr[3], 0x7632));
            oa.z = badd2(xa.z, prmt(pr[4], pr[5], 0x5410)); ob.z = badd2(xb.z, prmt(pr[4], pr[5], 0x7632));
            oa.w = badd2(xa.w, prmt(pr[6], pr[7], 0x5410)); ob.w = badd2(xb.w, prmt(pr[6], pr[7], 0x7632));
            TS(14 + 4 * (s & 2));
            if (rel < 64) {
                uint4* op = (uint4*)(P.out + (uint32_t)((512 * s + 128 * c + 64 * rank + 2 * lane) * DM + 8 * q));
                if (rel != 2 * lane) op[0] = oa;
                if (rel != 2 * lane + 1) op[DM / 8] = ob;
            } else {
                sts128(xs, oa.x, oa.y, oa.z, oa.w);
                sts128(xs + 512, ob.x, ob.y, ob.z, ob.w);
                fence_async();
                __syncwarp();
                if (elect()) {
                    asm volatile("cp.async.bulk.tensor.4d.global.shared::cta.bulk_group [%0,{%2,%3,0,%4}],[%1];"
                                 ::"l"(&tm.m[4]), "r"(sb + OFF_XS + (4 * s + c) * 1024), "r"(8 * q), "r"(32 * rank), "r"(4 * s + c) : "memory");
                    asm volatile("cp.async.bulk.commit_group;" ::: "memory");
                }
                __syncwarp();
            }
            xs += 8192; ys += 8192; rel -= 1024;
            TS(12 + 4 * (s & 2));
        }
        if (I0 == 7) *epoch = ep ^ G_BUF;
        asm volatile("cp.async.bulk.wait_group.read 0;" ::: "memory");
        TS_END();
        }
    } else {
      if (b > 128) return;
      if (wg == 4) {
        TS(10);
        asm volatile("setmaxnreg.dec.sync.aligned.u32 48;");
        uint4 p4, p5;
        if (c == 3) { p4 = ldg128((const uint4*)P.wr + lane); p5 = ldg128((const uint4*)P.wr + 32 + lane); }
        if (elect()) {
            const uint32_t a = bar0 + 8 * c;
#pragma unroll
            for (int i = 0; i < 10; i++) mbar_init(a + 32 * i, i < 4 || i == 8 ? 1 : i == 4 ? 2 : i < 8 ? (c == 1 ? 6 : 2) : c == 2 ? 4 : 1);
#pragma unroll
            for (int i = 0; i < 9; i++) mbar_expect(a + 32 * i, i < 4 ? 1024 : i < 8 ? 512 : 4096);
            if (c == 0) mbar_expect(a + 288, 32768);
            asm volatile("fence.mbarrier_init.release.cluster;" ::: "memory");
        }
        __syncwarp();
        asm volatile("barrier.cluster.arrive.relaxed.aligned;" ::: "memory");
        if (b == 128) return;
        if (elect()) asm volatile("prefetch.tensormap [%0];" ::"l"(&tm.m[c == 0 ? 3 : c == 1 ? b / 43 : 4]) : "memory");
        if (c == 3) {
            float sm[4] = {};
            mma16bf(sm, p4.x, p4.y, p4.z, p4.w, 0x3f803f80u, 0x3f803f80u);
            mma16bf(sm, p5.x, p5.y, p5.z, p5.w, 0x3f803f80u, 0x3f803f80u);
            float wsum = sm[0] + sm[2];
#pragma unroll
            for (int o = 4; o < 32; o <<= 1) wsum += __shfl_xor_sync(0xffffffffu, wsum, o);
            sts32(sb + OFF_KEY + 4, __float_as_uint(wsum));
            bar_arrive(10, 160);
        }
        if (c < 2) {
            asm volatile("barrier.cluster.wait.acquire.aligned;" ::: "memory");
            if (elect()) {
#pragma unroll 1
                for (int i = 0; i < (c ? (b >= 86 ? 0 : 8) : XS_N); i++) {
                    while ((uint32_t)clock() - t_entry < (c ? WT_T0 + WT_DT * i : XS_T0 + XS_DT * i)) {}
                    if (c) tma4d(sb + OFF_WT + 4096 * i, &tm.m[b >= 43], bar0 + 8 * B_WT, 0, 0, i, b >= 43 ? b - 43 : b);
                    else tma4d(sb + OFF_XS + 1024 * i, &tm.m[3], bar0 + 8 * (B_X + (i >> 2)), 8 * q, 32 * rank, 0, i);
                }
            }
            __syncwarp();
            TS(2);
        }
        uint32_t ub = sb + OFF_KS + c * CH_STRIDE + U_OFF + lane * 16, so = sb + OFF_S + c * S_STRIDE + lane * 16;
        bar_sync(11, 384);
        const uint32_t o7 = SG_S7 + ((lane ^ ((lane >> 3) & 1)) - lane) * 16, o9 = SG_S9 + (((lane + 1) ^ (((lane + 1) >> 3) & 1)) - lane) * 16;
        if (lane == 0) sts128(so + SG_S9, 0, 0, 0, 0);
        TS(3);
#pragma unroll 1
        for (int s = 0; s < 3; s++) {
#pragma unroll 1
            for (int k = 0; k < 4; k++) mbar_wait(bar0 + 8 * (B_U + 4 * s + k));
            uint4 c0[2], c1[2];
            uint2 c2[2];
#pragma unroll
            for (int h = 0; h < 2; h++) { c0[h] = lds128(ub + h * 512); c1[h] = lds128(ub + h * 512 - 16); c2[h] = lds64(ub + h * 512 - 24); }
            ub += 1024;
#pragma unroll
            for (int h = 0; h < 2; h++, so += 512) {
                const uint4 b0 = c0[h], b1 = c1[h];
                const uint2 b2 = c2[h];
                const uint32_t e[9] = {b2.x, b2.y, b1.x, b1.y, b1.z, b1.w, b0.x, b0.y, b0.z};
                uint32_t od[9], E[8], T3[5], Qs[8], T5[5];
#pragma unroll
                for (int j = 1; j < 9; j++) od[j] = prmt(e[j - 1], e[j], 0x5432);
#pragma unroll
                for (int j = 1; j < 8; j++) E[j] = hadd2(e[j], od[j]);
#pragma unroll
                for (int j = 0; j < 5; j++) T3[j] = hadd2(od[j + 4], E[j + 3]);
#pragma unroll
                for (int j = 2; j < 8; j++) Qs[j] = hadd2(E[j], E[j - 1]);
#pragma unroll
                for (int j = 0; j < 5; j++) T5[j] = hadd2(Qs[j + 2], e[j]);
                sts128(so + SG_S3, T3[1], T3[2], T3[3], T3[4]);
                sts128(so + SG_S5, T5[1], T5[2], T5[3], T5[4]);
                if (s < 2) {
                    sts128(so + o7, hadd2(T3[0], Qs[2]), hadd2(T3[1], Qs[3]), hadd2(T3[2], Qs[4]), hadd2(T3[3], Qs[5]));
                    sts128(so + o9, hadd2(Qs[4], T5[0]), hadd2(Qs[5], T5[1]), hadd2(Qs[6], T5[2]), hadd2(Qs[7], T5[3]));
                }
                TS(16 + 2 * s + h);
            }
            __syncwarp();
            if (lane == 0) mbar_arrive(bar0 + 8 * (s == 1 ? B_W : B_U + 5 + 4 * s));
            TS(4 + s);
        }
        TS_END();
      } else {
        const bool main_cta = b < 128;
        asm volatile("barrier.cluster.arrive.relaxed.aligned;" ::: "memory");
        TS(14);
        sts64(sb + OFF_YB + 8704 + (c >> 1) * 9216 + (c & 1) * 256 + lane * 8, 0x3f803f80u, 0x3f803f80u);
        unsigned* const scr = P.scr + ep;
        uint4 kv;
        const int xt = 32 * c + lane;
        uint32_t gkey = 0;
        unsigned* const ps = scr + (lane < 16 ? G_STATS + 128 * lane : G_KEY) + b;
        if (main_cta) {
            const uint64_t dl = mkdesc(sb + OFF_YB, 16, 1024) | SW128;
            const uint32_t la = sb + OFF_YB + 18432 + g * 16 + c * 4;
            asm volatile("cp.async.wait_all;" ::: "memory");
            TS(13);
            fence_async();
            bar_sync(7, 128);
            TS(1);
            float L[36];
            asm volatile("wgmma.fence.sync.aligned;" ::: "memory");
            wg_ln<0>(L, dl);
#pragma unroll
            for (int k = 1; k < 8; k++) wg_ln<1>(L, dl + (k >> 2) * 576 + (k & 3) * 2);
            asm volatile("wgmma.commit_group.sync.aligned;" ::: "memory");
            asm volatile("wgmma.wait_group.sync.aligned 0;" ::: "memory");
            asm volatile("" : F8(L, 0), F8(L, 8), F8(L, 16), F8(L, 24), "+f"(L[32]), "+f"(L[33]), "+f"(L[34]), "+f"(L[35]));
            bar_arrive(5, 640);
            TS(11);
            float e[4];
#pragma unroll
            for (int k = 0; k < 4; k++) {
                const int o = (k & 1) + 6 * (k >> 1);
                const float lo = (c & 1) ? L[8 + o] : L[o], hi = (c & 1) ? L[24 + o] : L[16 + o];
                e[k] = (c & 2) ? hi : lo;
            }
            if (t == (g >> 1)) { sts32(la, __float_as_uint((g & 1) ? e[1] : e[0])); sts32(la + 128, __float_as_uint((g & 1) ? e[3] : e[2])); }
            if ((t & 1) == (c >> 1)) {
                const uint32_t lb = la + 256 + (t >> 1) * 256;
                sts32(lb, __float_as_uint((c & 1) ? L[33] : L[32]));
                sts32(lb + 128, __float_as_uint((c & 1) ? L[35] : L[34]));
            }
        }
        if (main_cta) {
            bar_sync(10, 160);
            TS(12);
            if (c == 0) {
                const int row = 128 * (lane & 15) + b;
                const uint32_t lr = sb + OFF_YB + 18432 + (lane & 15) * 16;
                const uint4 q2 = lds128(lr), qw = lds128(lr + 256), q1 = lds128(lr + 512);
                const float mean = ((__uint_as_float(q1.x) + __uint_as_float(q1.y)) + (__uint_as_float(q1.z) + __uint_as_float(q1.w))) * (1.f / DM);
                float var = fmaf(-mean, mean, ((__uint_as_float(q2.x) + __uint_as_float(q2.y)) + (__uint_as_float(q2.z) + __uint_as_float(q2.w))) * (1.f / DM));
                const float mb = bf16r(mean);
                float rs = fmaf(-mb, __uint_as_float(lds32(sb + OFF_KEY + 4)), (__uint_as_float(qw.x) + __uint_as_float(qw.y)) + (__uint_as_float(qw.z) + __uint_as_float(qw.w)));
                if (mean * mean > 64.f * var) {
                    var = 0.f; rs = 0.f;
#pragma unroll 1
                    for (int k = 0; k < DM; k++) {
                        const float xv = ldbf(P.x + (uint32_t)(row * DM + k));
                        var = fmaf(xv - mean, xv - mean, var);
                        rs = fmaf(xv - mb, ldbf(P.wr + k), rs);
                    }
                    var *= 1.f / DM;
                }
                float sd; asm("sqrt.approx.ftz.f32 %0,%1;" : "=f"(sd) : "f"(bf16r(bf16r(var) + 1e-5f)));
                const uint32_t sw = pack_b2(mb, sd) | 0x80000000u;
                if (lane < 16) publish(ps, sw);
                const uint32_t t_pub = (uint32_t)clock();
                if (EPAUSE == 2) { __syncwarp(); bar_arrive(13, 288); }
                TS(2);
                rs = rs * -rcp(bhi(sw)) + 0.f;
                const int rb = (int)pack_b2(0.f, rs);
                const uint32_t u = (uint32_t)(rb ^ ((rb >> 31) | 0x80000000)) >> 16;
                gkey = __reduce_max_sync(0xffffffffu, ((rs != rs ? 0u : u) << 11) | (uint32_t)(2047 - row));
                if (lane == 16) publish(ps, gkey | 0x80000000u);
                TS(3);
                while ((uint32_t)clock() - t_pub < POLL_D) {}
                bar_arrive(6, 320);
            }
        }
        asm volatile("setmaxnreg.dec.sync.aligned.u32 48;");
        asm volatile("barrier.cluster.wait.acquire.aligned;" ::: "memory");
        if (main_cta) {
            if (c == 3) {
                bar_sync(6, 320);
                int it = 0;
                do { kv = ld_rlx4(scr + G_KEY + 4 * lane); } while (!__all_sync(0xffffffffu, (int)(kv.x & kv.y & kv.z & kv.w) < 0) && ++it < SPIN_LIMIT);
                gkey = __reduce_max_sync(0xffffffffu, max(max(kv.x, kv.y), max(kv.z, kv.w)));
                if (lane == 0) {
                    sts32(sb + OFF_KEY, gkey);
                    mbar_arrive(bar0 + 8 * B_K);
                }
                TS(4);
            }
        }
        const bool first = b < 86;
        if (!first && c == 2 && elect()) {
#pragma unroll 1
            for (int i = 0; i < 8; i++) {
                while ((uint32_t)clock() - t_entry < WD_T0 + WD_DT * i) {}
                tma4d(sb + OFF_WT + 4096 * i, &tm.m[2], bar0 + 8 * B_WT, 0, 0, i, b - 86);
            }
        }
        __syncwarp();
        if (!first && c == 1) {
            const unsigned* pp = scr + G_PRE + 32 * (b - 86) + lane;
            const uint32_t ha = sb + OFF_XSEL + mi * 128 + rw * 2;
            sts128(sb + OFF_XSEL + lane * 16, 0, 0, 0, 0);
            sts128(sb + OFF_XSEL + 512 + lane * 16, 0, 0, 0, 0);
            uint32_t v0, v1, v2, v3;
            int it = 0;
            do {
                v0 = ld_rlx(pp); v1 = ld_rlx(pp + FF); v2 = ld_rlx(pp + 2 * FF); v3 = ld_rlx(pp + 3 * FF);
            } while (!__all_sync(0xffffffffu, v0 & v1 & v2 & v3 & 1) && ++it < SPIN_LIMIT);
            TS(5);
            const uint32_t gu = pack_b2(__uint_as_float(v0) + __uint_as_float(v1), __uint_as_float(v2) + __uint_as_float(v3));
            const uint32_t hv = pack_b2(bf16r(silu(blo(gu))) * bhi(gu), 0.f);
            sts16(ha, hv); sts16(ha + 32, hv); sts16(ha + 512 + 64, hv); sts16(ha + 512 + 96, hv);
        }
        uint32_t st = 0;
        if (first && c != 3) {
            mbar_wait(bar0 + 8 * B_K);
            gkey = lds32(sb + OFF_KEY);
        }
        const uint32_t idx = ~gkey & 2047u;
        if (first || (main_cta && c == 3)) {
            const uint2 xv = __ldg((const uint2*)P.x + idx * (DM / 4) + xt);
            int it = 0;
            do { st = ld_rlx(scr + G_STATS + idx); } while (!__all_sync(0xffffffffu, (int)st < 0) && ++it < SPIN_LIMIT);
            if (first) {
                const float ri = rcp(__uint_as_float(st & 0x7fff0000u));
                const uint32_t d0 = bsub2l(xv.x, st), d1 = bsub2l(xv.y, st);
                const uint32_t xo = sb + OFF_XSEL + (xt >> 2) * 32 + t * 4;
                sts32(xo, pack_b2(blo(d0) * ri, blo(d1) * ri));
                sts32(xo + 16, pack_b2(bhi(d0) * ri, bhi(d1) * ri));
            }
        }
        {
            uint64_t dw0 = mkdesc(sb + OFF_WT, 16, 1024) | SW128, dx = mkdesc(sb + OFF_XSEL, first ? 32 : 128);
            const uint32_t s0 = first ? 16 : 0, s1 = first ? 4 : 16;
            const int col = 64 * b + 16 * c;
            const bool odd = (col / FF) & 1;
            unsigned* dst = scr + (first ? G_PRE + col + 8 * t + g : G_SUM + 2 * (128 * c + 8 * t + g));
            fence_async();
            mbar_wait(bar0 + 8 * B_WT);
            bar_sync(7, 128);
            TS(first ? 7 : 17);
            float a[4][4];
            asm volatile("wgmma.fence.sync.aligned;" ::: "memory");
#pragma unroll 1
            for (int j = 0; j < 4; j++, dw0 += 128, dx += s1) {
#pragma unroll
                for (int k = 0; k < 4; k++) wg_gemv(a[k], dw0 + 512 * k, dx + k * s0, j);
            }
            asm volatile("wgmma.commit_group.sync.aligned;" ::: "memory");
            asm volatile("wgmma.wait_group.sync.aligned 0;" ::: "memory");
#pragma unroll
            for (int k = 0; k < 4; k++) asm volatile("" : "+f"(a[k][0]), "+f"(a[k][1]), "+f"(a[k][2]), "+f"(a[k][3]));
            if (first) {
                const float v0 = odd ? (a[0][1] + a[1][1]) + (a[2][1] + a[3][1]) : (a[0][0] + a[1][0]) + (a[2][0] + a[3][0]);
                float v1 = odd ? (a[0][3] + a[1][3]) + (a[2][3] + a[3][3]) : (a[0][2] + a[1][2]) + (a[2][2] + a[3][2]);
                v1 = __shfl_up_sync(0xffffffffu, v1, 1);
                if (t < 2) publish(dst, __float_as_uint(t ? v1 : v0) | 1u);
            } else {
#pragma unroll
                for (int k = 0; k < 4; k++) {
                    const long long f = __float2ll_rn(((t & 1) ? a[k][2] : a[k][0]) * 67108864.f);
                    asm volatile("red.relaxed.gpu.global.add.u64 [%0],%1;" ::"l"(dst + 64 * k), "l"((f & ~63ll) | 1) : "memory");
                }
                if (!main_cta && c == 0) *epoch = ep ^ G_BUF;
            }
        }
        TS(first ? 8 : 18);
        if (main_cta && c == 3 && ((idx >> 6) & 1) == rank) {
            const unsigned* pp = scr + G_SUM + 2 * (128 * ((q >> 1) & 3) + 16 * (q >> 3) + 8 * (q & 1) + rw);
            const uint32_t dsk = __ldg((const unsigned short*)P.Dskip + 8 * q + rw);
            const uint32_t xv = __ldg((const unsigned short*)P.x + (idx * DM + 8 * q + rw));
            const int u = (int)(gkey << 5);
            const float rv = __uint_as_float((uint32_t)(u ^ ((~u >> 31) | 0x80000000)) & 0xffff0000u);
            const uint32_t rsel = pack_b2(rcp(1.f + ex2(-1.4426950408889634f * rv)), 0.f);
            const uint32_t xn = pack_b2(blo(bsub2(xv, st)) * rcp(__uint_as_float(st & 0x7fff0000u)), 0.f);
            const uint32_t t1 = bmul2(xn, dsk), yad = sb + OFF_YB + (idx >> 7) * 1024 + rw * 128 + (idx & 63) * 2;
            unsigned short* const op = (unsigned short*)P.out + (idx * DM + 8 * q + rw);
            uint2 f;
            int it = 0;
            do { f = ld_rlx2(pp); } while (!__all_sync(0xffffffffu, (f.x & 63u) == 43u) && ++it < SPIN_LIMIT);
            TS(9);
            const float s = __ll2float_rn((long long)(((unsigned long long)f.y << 32) | (f.x & ~63u))) * (1.f / 67108864.f);
            const uint32_t gv = pack_b2(silu(blo(badd2(xn, bmul2(pack_b2(s, 0.f), rsel)))), 0.f);
            mbar_wait_long(bar0 + 8 * (B_Y + (idx >> 7)));
            const uint32_t ov = badd2(xv, bmul2(badd2(lds16(yad), t1), gv));
            if (lane < 8) *op = (unsigned short)ov;
            TS(10);
        }
        TS_END();
      }
    }
}

typedef CUresult (*EncodeFn)(CUtensorMap*, CUtensorMapDataType, cuuint32_t, void*, const cuuint64_t*, const cuuint64_t*,
                             const cuuint32_t*, const cuuint32_t*, CUtensorMapInterleave, CUtensorMapSwizzle,
                             CUtensorMapL2promotion, CUtensorMapFloatOOBfill);

void encode4d(EncodeFn fn, CUtensorMap* m, const void* p, uint64_t d0, uint64_t d1, uint64_t d2, uint64_t d3, uint64_t s1, uint64_t s2,
              uint64_t s3, uint32_t b0, uint32_t b1, uint32_t b2, CUtensorMapSwizzle sw) {
    cuuint64_t gd[4] = {d0, d1, d2, d3};
    cuuint64_t gs[3] = {s1, s2, s3};
    cuuint32_t bd[4] = {b0, b1, b2, 1};
    cuuint32_t es[4] = {1, 1, 1, 1};
    fn(m, CU_TENSOR_MAP_DATA_TYPE_BFLOAT16, 4, const_cast<void*>(p), gd, gs, bd, es, CU_TENSOR_MAP_INTERLEAVE_NONE, sw,
       CU_TENSOR_MAP_L2_PROMOTION_NONE, CU_TENSOR_MAP_FLOAT_OOB_FILL_NONE);
}

}

extern "C" void kernel_launch(void* const* d_in, const int* in_sizes, int n_in, void* d_out, int out_size) {
    static EncodeFn fn = nullptr;
    static unsigned* scr = nullptr;
    static const uint4* dst = nullptr;
    if (!fn) {
        void* p = nullptr;
        cudaDriverEntryPointQueryResult qr;
        cudaGetDriverEntryPoint("cuTensorMapEncodeTiled", &p, cudaEnableDefault, &qr);
        fn = (EncodeFn)p;
        cudaGetSymbolAddress(&p, g_scr);
        scr = (unsigned*)p;
        cudaGetSymbolAddress(&p, g_dst);
        dst = (const uint4*)p;
        cudaFuncSetAttribute(s4d_fused_kernel, cudaFuncAttributeMaxDynamicSharedMemorySize, SMEM_BYTES + SMEM_EXTRA);
    }
    Maps tm;
    encode4d(fn, &tm.m[0], d_in[9], 64, 32, 8, 43, 4 * FF, 32 * 4 * FF, 128, 64, 32, 1, CU_TENSOR_MAP_SWIZZLE_128B);
    encode4d(fn, &tm.m[1], d_in[10], 64, 32, 8, 43, 4 * FF, 32 * 4 * FF, 128, 64, 32, 1, CU_TENSOR_MAP_SWIZZLE_128B);
    encode4d(fn, &tm.m[2], d_in[11], 64, 32, 8, 43, DM * 2, 128, 32 * DM * 2, 64, 32, 1, CU_TENSOR_MAP_SWIZZLE_128B);
    encode4d(fn, &tm.m[3], d_in[0], DM, 64, 2, 16, DM * 4, DM * 2, 128 * DM * 2, 8, 32, 2, CU_TENSOR_MAP_SWIZZLE_NONE);
    encode4d(fn, &tm.m[4], d_out, DM, 64, 2, 16, DM * 4, DM * 2, 128 * DM * 2, 8, 32, 2, CU_TENSOR_MAP_SWIZZLE_NONE);
    Params P;
    P.x = (const __nv_bfloat16*)d_in[0];
    P.logA = (const __nv_bfloat16*)d_in[1];
    P.Aim = (const __nv_bfloat16*)d_in[2];
    P.Cr = (const __nv_bfloat16*)d_in[3];
    P.Ci = (const __nv_bfloat16*)d_in[4];
    P.logdt = (const __nv_bfloat16*)d_in[5];
    P.Dskip = (const __nv_bfloat16*)d_in[6];
    P.wr = (const __nv_bfloat16*)d_in[8];
    P.out = (__nv_bfloat16*)d_out;
    P.scr = scr;
    P.dst = dst;
    s4d_fused_kernel<<<NCTA, NTHREADS, SMEM_BYTES + SMEM_EXTRA, cudaStreamPerThread>>>(P, tm);
}
```
